```python
import torch

def _softmax(x, axis=-1):
    return torch.softmax(x, dim=axis)
def _gelu(x):
    return torch.nn.functional.gelu(x, approximate="tanh")
def _silu(x):
    return torch.nn.functional.silu(x)
def _sigmoid(x):
    return torch.sigmoid(x)
def _layernorm(x, axis=-1, eps=1e-5):
    m = x.mean(dim=axis, keepdim=True)
    v = x.var(dim=axis, keepdim=True, unbiased=False)
    return (x - m) / torch.sqrt(v + eps)
def _scatter_add(tgt, idx, src, axis=0):
    return tgt.clone().index_add_(axis, idx, src)
def _segment_sum(src, seg, n):
    out = torch.zeros((n,) + src.shape[1:], dtype=src.dtype)
    return out.index_add_(0, seg, src)
def _pad(x, pw):
    flat = tuple(v for pair in reversed(pw) for v in pair)
    return torch.nn.functional.pad(x, flat)

kernel_name = 'concat_heads__mha_block_cached__mha_block_cached__near_ridge'

def setup_inputs():

    _w = (lambda a: (lambda t: t.to(torch.bfloat16) if t.is_floating_point() else t)(torch.as_tensor(a)))
    def _A_setup():
        B, Sq, D = 8, 96, 640
        H, Sk, Dh = 32, 512, 192
        return {
            "x": _w((lambda *s: torch.randn(*s, dtype=torch.bfloat16) * 0.8)(B, Sq, D)),
            "k_cache": _w((lambda *s: torch.randn(*s, dtype=torch.bfloat16) * 0.8)(B, H, Sk, Dh)),
            "v_cache": _w((lambda *s: torch.randn(*s, dtype=torch.bfloat16) * 0.05)(B, H, Sk, Dh)),
            "wq": _w((lambda *s: torch.randn(*s, dtype=torch.bfloat16) * 0.8)(D, H * Dh) * (D ** -0.5)),
            "wo": _w((lambda *s: torch.randn(*s, dtype=torch.bfloat16) * 0.05)(H * Dh, D) * ((H * Dh) ** -0.5)),
        }
    _A_in = _A_setup()

    def _B_setup():
        B, Sq, D = 8, 96, 640
        H, Sk, Dh = 32, 512, 192
        return {
            "x": _w((lambda *s: torch.randn(*s, dtype=torch.bfloat16) * 0.8)(B, Sq, D)),
            "k_cache": _w((lambda *s: torch.randn(*s, dtype=torch.bfloat16) * 0.8)(B, H, Sk, Dh)),
            "v_cache": _w((lambda *s: torch.randn(*s, dtype=torch.bfloat16) * 0.05)(B, H, Sk, Dh)),
            "wq": _w((lambda *s: torch.randn(*s, dtype=torch.bfloat16) * 0.8)(D, H * Dh) * (D ** -0.5)),
            "wo": _w((lambda *s: torch.randn(*s, dtype=torch.bfloat16) * 0.05)(H * Dh, D) * ((H * Dh) ** -0.5)),
        }
    _B_in = _B_setup()

    return {
        "A_x": _A_in["x"],
        "A_k_cache": _A_in["k_cache"],
        "A_v_cache": _A_in["v_cache"],
        "A_wq": _A_in["wq"],
        "A_wo": _A_in["wo"],
        "B_x": _B_in["x"],
        "B_k_cache": _B_in["k_cache"],
        "B_v_cache": _B_in["v_cache"],
        "B_wq": _B_in["wq"],
        "B_wo": _B_in["wo"],
    }

def reference(A_x, A_k_cache, A_v_cache, A_wq, A_wo, B_x, B_k_cache, B_v_cache, B_wq, B_wo):
    def _A_ref(x, k_cache, v_cache, wq, wo):
        B, Sq, D = x.shape
        H, Dh = 32, 192
        q = (lambda x, *d: x.permute(*d))((x @ wq).reshape(B, Sq, H, Dh), 0, 2, 1, 3)
        scores = torch.einsum("bhqd,bhkd->bhqk", q, k_cache) * (Dh ** -0.5)
        p = _softmax(scores, axis=-1)
        o = torch.einsum("bhqk,bhkd->bhqd", p, v_cache)
        return (lambda x, *d: x.permute(*d))(o, 0, 2, 1, 3).reshape(B, Sq, H * Dh) @ wo

    def _B_ref(x, k_cache, v_cache, wq, wo):
        B, Sq, D = x.shape
        H, Dh = 32, 192
        q = (lambda x, *d: x.permute(*d))((x @ wq).reshape(B, Sq, H, Dh), 0, 2, 1, 3)
        scores = torch.einsum("bhqd,bhkd->bhqk", q, k_cache) * (Dh ** -0.5)
        p = _softmax(scores, axis=-1)
        o = torch.einsum("bhqk,bhkd->bhqd", p, v_cache)
        return (lambda x, *d: x.permute(*d))(o, 0, 2, 1, 3).reshape(B, Sq, H * Dh) @ wo

    a = _A_ref(A_x, A_k_cache, A_v_cache, A_wq, A_wo)
    b = _B_ref(B_x, B_k_cache, B_v_cache, B_wq, B_wo)
    return torch.concatenate([a, b], axis=-1)
```

```cpp
#include <cuda_runtime.h>
#include <cuda_bf16.h>
#include <cuda.h>
#include <stdint.h>

namespace {

constexpr int NB = 8, SQ = 96, DM = 640, NH = 32, SK = 512, DH = 192;
constexpr int NCTA = 128;
constexpr int REG_ATTN = 232, REG_PROJ = 240, REG_PROD = 32;
constexpr int P_A = 8;
constexpr int P_OB = 2;
constexpr int NP = 7, NW = 5;
constexpr int PC_BYTES = 8192, W_BYTES = 24576, QC_BYTES = 12288;
constexpr int OFF_Q = 0;
constexpr int OFF_P = 3 * QC_BYTES;
constexpr int OFF_KV = 4 * QC_BYTES;
constexpr int OFF_W = OFF_KV + NP * PC_BYTES;
constexpr int OFF_ST = OFF_W + NW * W_BYTES;
constexpr int OFF_BAR = OFF_ST + 1536 + 3 * 384 + 16;
constexpr int SMEM_BYTES = OFF_BAR + 288;
static_assert(SMEM_BYTES <= 232448, "smem");
constexpr int OSC_CHUNK = 768 * 128;

struct Maps { CUtensorMap k[2], v[2], wq[2], x[2], wo[2]; };

__device__ __align__(1024) unsigned char g_oscr[2 * P_OB * 8 * 3 * OSC_CHUNK];
__device__ unsigned g_cons[2 * 4];
__device__ unsigned g_flag[2 * NB * NH];
__device__ unsigned g_epoch;
__device__ unsigned g_done;
#define TL(i)
#define TLV(i, v)
#define CLK() 0LL
#define TR(k, n)

__device__ __forceinline__ uint32_t s2u(const void* p) { return (uint32_t)__cvta_generic_to_shared(p); }
__device__ __forceinline__ void mbar_init(uint32_t b, int c) { asm volatile("mbarrier.init.shared.b64 [%0], %1;" ::"r"(b), "r"(c)); }
__device__ __forceinline__ void mbar_expect(uint32_t b, uint32_t bytes) {
  asm volatile("mbarrier.arrive.expect_tx.shared.b64 _, [%0], %1;" ::"r"(b), "r"(bytes) : "memory");
}
__device__ __forceinline__ void mbar_arrive(uint32_t b) { asm volatile("mbarrier.arrive.shared.b64 _, [%0];" ::"r"(b) : "memory"); }
__device__ __forceinline__ void mbar_wait(uint32_t b, uint32_t ph) {
  asm volatile(
      "{\n.reg .pred p;\n.reg .u32 c;\nmov.u32 c, 0;\n"
      "WL:\nmbarrier.try_wait.parity.shared.b64 p, [%0], %1;\n@p bra WD;\n"
      "add.u32 c, c, 1;\nsetp.lt.u32 p, c, 0x4000000;\n@p bra WL;\ntrap;\nWD:\n}\n" ::"r"(b), "r"(ph) : "memory");
}
__device__ __forceinline__ void smem_wait_ge(uint32_t a, uint32_t v) {
  asm volatile(
      "{\n.reg .pred p;\n.reg .u32 c, x;\nmov.u32 c, 0;\n"
      "SL:\nld.acquire.cta.shared.u32 x, [%0];\nsetp.ge.u32 p, x, %1;\n@p bra SD;\n"
      "add.u32 c, c, 1;\nsetp.lt.u32 p, c, 0x40000000;\n@p bra SL;\ntrap;\nSD:\n}\n" ::"r"(a), "r"(v) : "memory");
}
__device__ __forceinline__ bool mbar_test(uint32_t b, uint32_t ph) {
  uint32_t ok;
  asm volatile("{\n.reg .pred p;\nmbarrier.test_wait.parity.shared.b64 p, [%1], %2;\nselp.u32 %0, 1, 0, p;\n}\n" : "=r"(ok) : "r"(b), "r"(ph) : "memory");
  return ok != 0;
}
__device__ __forceinline__ void tma2d(uint32_t dst, const CUtensorMap* m, int c0, int c1, uint32_t bar) {
  asm volatile("cp.async.bulk.tensor.2d.shared::cluster.global.mbarrier::complete_tx::bytes [%0], [%1, {%3, %4}], [%2];"
               ::"r"(dst), "l"(m), "r"(bar), "r"(c0), "r"(c1) : "memory");
}
__device__ __forceinline__ void tma2d_hint(uint32_t dst, const CUtensorMap* m, int c0, int c1, uint32_t bar, uint64_t pol) {
  asm volatile("cp.async.bulk.tensor.2d.shared::cluster.global.mbarrier::complete_tx::bytes.L2::cache_hint [%0], [%1, {%3, %4}], [%2], %5;"
               ::"r"(dst), "l"(m), "r"(bar), "r"(c0), "r"(c1), "l"(pol) : "memory");
}
__device__ __forceinline__ void tma3d_mc(uint32_t dst, const CUtensorMap* m, int c0, int c1, int c2, uint32_t bar) {
  asm volatile("cp.async.bulk.tensor.3d.shared::cluster.global.mbarrier::complete_tx::bytes.multicast::cluster [%0], [%1, {%3, %4, %5}], [%2], %6;"
               ::"r"(dst), "l"(m), "r"(bar), "r"(c0), "r"(c1), "r"(c2), "h"((uint16_t)3) : "memory");
}
__device__ __forceinline__ void bulk_load_mc(uint32_t dst, const void* src, uint32_t bytes, uint32_t bar) {
  asm volatile("cp.async.bulk.shared::cluster.global.mbarrier::complete_tx::bytes.multicast::cluster [%0], [%1], %2, [%3], %4;"
               ::"r"(dst), "l"(src), "r"(bytes), "r"(bar), "h"((uint16_t)3) : "memory");
}
__device__ __forceinline__ void bulk_load(uint32_t dst, const void* src, uint32_t bytes, uint32_t bar) {
  asm volatile("cp.async.bulk.shared::cluster.global.mbarrier::complete_tx::bytes [%0], [%1], %2, [%3];"
               ::"r"(dst), "l"(src), "r"(bytes), "r"(bar) : "memory");
}
__device__ __forceinline__ void mbar_arrive_pair(uint32_t b, uint32_t peer) {
  asm volatile("{\n.reg .b32 r;\nmapa.shared::cluster.u32 r, %0, %1;\nmbarrier.arrive.shared::cluster.b64 _, [r];\n"
               "mbarrier.arrive.shared.b64 _, [%0];\n}\n" ::"r"(b), "r"(peer) : "memory");
}
__device__ __forceinline__ void cluster_sync() {
  asm volatile("barrier.cluster.arrive.release.aligned;\nbarrier.cluster.wait.acquire.aligned;" ::: "memory");
}
__device__ __forceinline__ void wg_fence() { asm volatile("wgmma.fence.sync.aligned;" ::: "memory"); }
__device__ __forceinline__ void wg_commit() { asm volatile("wgmma.commit_group.sync.aligned;" ::: "memory"); }
template <int N> __device__ __forceinline__ void wg_wait() { asm volatile("wgmma.wait_group.sync.aligned %0;" ::"n"(N) : "memory"); }
template <int N> __device__ __forceinline__ void fence_regs(float (&d)[N]) {
#pragma unroll
  for (int i = 0; i < N; i++) asm volatile("" : "+f"(d[i])::"memory");
}
__device__ __forceinline__ uint64_t desc(uint32_t a4) { return (uint64_t)(a4 | (1u << 16)) | ((uint64_t)(64u | (1u << 30)) << 32); }
__device__ __forceinline__ uint64_t desc64(uint32_t a4) { return (uint64_t)(a4 | (1u << 16)) | ((uint64_t)(32u | (2u << 30)) << 32); }
__device__ __forceinline__ uint32_t pack_bf16(float lo, float hi) {
  uint32_t r;
  asm("cvt.rn.bf16x2.f32 %0, %1, %2;" : "=r"(r) : "f"(hi), "f"(lo));
  return r;
}
__device__ __forceinline__ float ex2(float x) { float y; asm("ex2.approx.ftz.f32 %0, %1;" : "=f"(y) : "f"(x)); return y; }
__device__ __forceinline__ void stsm_x4_t(uint32_t addr, uint32_t r0, uint32_t r1, uint32_t r2, uint32_t r3) {
  asm volatile("stmatrix.sync.aligned.m8n8.x4.trans.shared.b16 [%0], {%1,%2,%3,%4};" ::"r"(addr), "r"(r0), "r"(r1), "r"(r2), "r"(r3));
}
__device__ __forceinline__ unsigned ld_acquire(const unsigned* p) {
  unsigned v; asm volatile("ld.acquire.gpu.global.u32 %0, [%1];" : "=r"(v) : "l"(p) : "memory"); return v;
}

__device__ __forceinline__ void wgmma_s96(float (&d)[48], uint64_t da, uint64_t db, int sd){
  asm volatile("{\n.reg .pred p;\nsetp.ne.b32 p, %50, 0;\n"
    "wgmma.mma_async.sync.aligned.m64n96k16.f32.bf16.bf16 {%0,%1,%2,%3,%4,%5,%6,%7,%8,%9,%10,%11,%12,%13,%14,%15,%16,%17,%18,%19,%20,%21,%22,%23,%24,%25,%26,%27,%28,%29,%30,%31,%32,%33,%34,%35,%36,%37,%38,%39,%40,%41,%42,%43,%44,%45,%46,%47}, %48, %49, p, 1, 1, 0, 0;\n}\n"
    : "+f"(d[0]),"+f"(d[1]),"+f"(d[2]),"+f"(d[3]),"+f"(d[4]),"+f"(d[5]),"+f"(d[6]),"+f"(d[7]),"+f"(d[8]),"+f"(d[9]),"+f"(d[10]),"+f"(d[11]),"+f"(d[12]),"+f"(d[13]),"+f"(d[14]),"+f"(d[15]),"+f"(d[16]),"+f"(d[17]),"+f"(d[18]),"+f"(d[19]),"+f"(d[20]),"+f"(d[21]),"+f"(d[22]),"+f"(d[23]),"+f"(d[24]),"+f"(d[25]),"+f"(d[26]),"+f"(d[27]),"+f"(d[28]),"+f"(d[29]),"+f"(d[30]),"+f"(d[31]),"+f"(d[32]),"+f"(d[33]),"+f"(d[34]),"+f"(d[35]),"+f"(d[36]),"+f"(d[37]),"+f"(d[38]),"+f"(d[39]),"+f"(d[40]),"+f"(d[41]),"+f"(d[42]),"+f"(d[43]),"+f"(d[44]),"+f"(d[45]),"+f"(d[46]),"+f"(d[47])
    : "l"(da), "l"(db), "r"(sd));
}
__device__ __forceinline__ void wgmma_q96(float (&d)[48], uint64_t da, uint64_t db, int sd){
  asm volatile("{\n.reg .pred p;\nsetp.ne.b32 p, %50, 0;\n"
    "wgmma.mma_async.sync.aligned.m64n96k16.f32.bf16.bf16 {%0,%1,%2,%3,%4,%5,%6,%7,%8,%9,%10,%11,%12,%13,%14,%15,%16,%17,%18,%19,%20,%21,%22,%23,%24,%25,%26,%27,%28,%29,%30,%31,%32,%33,%34,%35,%36,%37,%38,%39,%40,%41,%42,%43,%44,%45,%46,%47}, %48, %49, p, 1, 1, 1, 0;\n}\n"
    : "+f"(d[0]),"+f"(d[1]),"+f"(d[2]),"+f"(d[3]),"+f"(d[4]),"+f"(d[5]),"+f"(d[6]),"+f"(d[7]),"+f"(d[8]),"+f"(d[9]),"+f"(d[10]),"+f"(d[11]),"+f"(d[12]),"+f"(d[13]),"+f"(d[14]),"+f"(d[15]),"+f"(d[16]),"+f"(d[17]),"+f"(d[18]),"+f"(d[19]),"+f"(d[20]),"+f"(d[21]),"+f"(d[22]),"+f"(d[23]),"+f"(d[24]),"+f"(d[25]),"+f"(d[26]),"+f"(d[27]),"+f"(d[28]),"+f"(d[29]),"+f"(d[30]),"+f"(d[31]),"+f"(d[32]),"+f"(d[33]),"+f"(d[34]),"+f"(d[35]),"+f"(d[36]),"+f"(d[37]),"+f"(d[38]),"+f"(d[39]),"+f"(d[40]),"+f"(d[41]),"+f"(d[42]),"+f"(d[43]),"+f"(d[44]),"+f"(d[45]),"+f"(d[46]),"+f"(d[47])
    : "l"(da), "l"(db), "r"(sd));
}
__device__ __forceinline__ void wgmma_o128(float (&d)[64], uint64_t da, uint64_t db, int sd){
  asm volatile("{\n.reg .pred p;\nsetp.ne.b32 p, %66, 0;\n"
    "wgmma.mma_async.sync.aligned.m64n128k16.f32.bf16.bf16 {%0,%1,%2,%3,%4,%5,%6,%7,%8,%9,%10,%11,%12,%13,%14,%15,%16,%17,%18,%19,%20,%21,%22,%23,%24,%25,%26,%27,%28,%29,%30,%31,%32,%33,%34,%35,%36,%37,%38,%39,%40,%41,%42,%43,%44,%45,%46,%47,%48,%49,%50,%51,%52,%53,%54,%55,%56,%57,%58,%59,%60,%61,%62,%63}, %64, %65, p, 1, 1, 1, 0;\n}\n"
    : "+f"(d[0]),"+f"(d[1]),"+f"(d[2]),"+f"(d[3]),"+f"(d[4]),"+f"(d[5]),"+f"(d[6]),"+f"(d[7]),"+f"(d[8]),"+f"(d[9]),"+f"(d[10]),"+f"(d[11]),"+f"(d[12]),"+f"(d[13]),"+f"(d[14]),"+f"(d[15]),"+f"(d[16]),"+f"(d[17]),"+f"(d[18]),"+f"(d[19]),"+f"(d[20]),"+f"(d[21]),"+f"(d[22]),"+f"(d[23]),"+f"(d[24]),"+f"(d[25]),"+f"(d[26]),"+f"(d[27]),"+f"(d[28]),"+f"(d[29]),"+f"(d[30]),"+f"(d[31]),"+f"(d[32]),"+f"(d[33]),"+f"(d[34]),"+f"(d[35]),"+f"(d[36]),"+f"(d[37]),"+f"(d[38]),"+f"(d[39]),"+f"(d[40]),"+f"(d[41]),"+f"(d[42]),"+f"(d[43]),"+f"(d[44]),"+f"(d[45]),"+f"(d[46]),"+f"(d[47]),"+f"(d[48]),"+f"(d[49]),"+f"(d[50]),"+f"(d[51]),"+f"(d[52]),"+f"(d[53]),"+f"(d[54]),"+f"(d[55]),"+f"(d[56]),"+f"(d[57]),"+f"(d[58]),"+f"(d[59]),"+f"(d[60]),"+f"(d[61]),"+f"(d[62]),"+f"(d[63])
    : "l"(da), "l"(db), "r"(sd));
}

template <int NJ>
__device__ __forceinline__ void store_tile_T(const float (&a)[NJ * 4], uint32_t base, int warp, int lane) {
  const int i = lane & 7, sel = lane >> 3;
  const int unit = 2 * warp + (sel & 1);
#pragma unroll
  for (int j = 0; j < NJ; j += 2) {
    const int row = 8 * (j + (sel >> 1)) + i;
    const uint32_t addr = base + row * 128 + ((unit ^ i) << 4);
    stsm_x4_t(addr, pack_bf16(a[4 * j + 0], a[4 * j + 1]), pack_bf16(a[4 * j + 2], a[4 * j + 3]),
              pack_bf16(a[4 * j + 4], a[4 * j + 5]), pack_bf16(a[4 * j + 6], a[4 * j + 7]));
  }
}

__global__ void __cluster_dims__(2, 1, 1) __launch_bounds__(384, 1)
fused_mha_kernel(const __grid_constant__ Maps maps, __nv_bfloat16* __restrict__ out) {
  extern __shared__ __align__(1024) unsigned char smem_raw[];
  const uint32_t sbase = s2u(smem_raw);
  if (sbase & 1023u) asm volatile("trap;");
  const uint32_t bar0 = sbase + OFF_BAR;
  const uint32_t kv_full = bar0, kv_empty = bar0 + 8 * NP, w_full = kv_empty + 8 * NP, w_empty = w_full + 8 * NW;
  const uint32_t q_ready = w_empty + 8 * NW, q_free = q_ready + 8, o_done = q_free + 8, ready_cnt = o_done + 8, war_ok = ready_cnt + 4, ord = ready_cnt + 8;
  const int tid = threadIdx.x, lane = tid & 31;
  const int wg = __shfl_sync(0xffffffffu, tid >> 7, 0), warp = __shfl_sync(0xffffffffu, (tid >> 5) & 3, 0);
  const int cta = blockIdx.x;
  const int rank = cta & 1;
  const uint32_t peer = rank ^ 1;
  const int blk = cta >> 6, hg = (cta >> 1) & 7, b = ((cta >> 4) & 3) * 2 + rank;
  const bool has_tile = cta < 120;
  const int oblk = (cta >> 1) / 30, orem = (cta >> 1) % 30, odt = (orem / 6) * 2 + rank, oqt = orem % 6;

  if (tid == 0) {
    for (int i = 0; i < NP; i++) { mbar_init(kv_full + 8 * i, 1); mbar_init(kv_empty + 8 * i, 1); }
    for (int i = 0; i < NW; i++) { mbar_init(w_full + 8 * i, 1); mbar_init(w_empty + 8 * i, 2); }
    mbar_init(q_ready, 128);
    mbar_init(q_free, 1);
    mbar_init(o_done, 128);
    asm volatile("st.shared.u32 [%0], 0;" ::"r"(ready_cnt) : "memory");
    asm volatile("st.shared.u32 [%0], 0;" ::"r"(war_ok) : "memory");
    asm volatile("fence.mbarrier_init.release.cluster;" ::: "memory");
    asm volatile("fence.proxy.async;" ::: "memory");
  }
  if (tid >= 32 && tid < 37) {
    const CUtensorMap* m = tid == 32 ? &maps.wq[blk] : tid == 33 ? &maps.x[blk] : tid == 34 ? &maps.k[blk] : tid == 35 ? &maps.v[blk] : &maps.wo[oblk & 1];
    asm volatile("prefetch.tensormap [%0];" ::"l"(m) : "memory");
  }
  __syncthreads();
  cluster_sync();

  if (tid == 0) TL(0);
  if (tid == 128) { TLV(1, CLK()); TR(11, 0); }
  if (wg == 2) {
    asm volatile("setmaxnreg.dec.sync.aligned.u32 %0;" ::"n"(REG_PROD));
    if (warp == 0 && lane == 0) {
      uint64_t pol;
      asm volatile("createpolicy.fractional.L2::evict_first.b64 %0, 1.0;" : "=l"(pol));
      const CUtensorMap* mk = &maps.k[blk];
      const CUtensorMap* mv = &maps.v[blk];
      int s = 0, ph = 1;
      for (int u = 0; u < 4; u++) {
        const int row0 = (b * NH + u * 8 + hg) * SK;
        for (int t = 0; t < 16; t++) {
#pragma unroll 1
          for (int c = 0; c < 3; c++) {
            mbar_wait(kv_empty + 8 * s, ph);
            if (c == 0) TR(6 + (t & 1), u * 8 + (t >> 1));
            tma2d_hint(sbase + OFF_KV + s * PC_BYTES, (t & 1) ? mv : mk, c * 64, row0 + (t >> 1) * 64, kv_full + 8 * s, pol);
            mbar_expect(kv_full + 8 * s, PC_BYTES);
            if (++s == NP) { s = 0; ph ^= 1; }
          }
        }
      }
    } else if (warp == 3) {
      const unsigned ep1 = ld_acquire(&g_epoch) + 1u;
      const unsigned target = 2u * ep1, target_c = 60u * ep1;
      int war = 0;
      unsigned listed = 0;
      const int b_sel = (oqt * 128 + ((lane & 1) ? 127 : 0)) / SQ;
      const unsigned* fp = &g_flag[(oblk * NB + b_sel) * NH + ((lane >> 1) & 7)];
      int pub = 0, nready = has_tile ? 0 : NH;
      unsigned spins = 0;
      while (pub < 4 || nready < NH) {
        if (pub < 4 && mbar_test(o_done, pub & 1)) {
          if (lane == 0) {
            asm volatile("fence.proxy.async.global;" ::: "memory");
            asm volatile("red.release.gpu.global.add.u32 [%0], 2;" ::"l"(&g_flag[(blk * NB + b) * NH + pub * 8 + hg]) : "memory");
            TL(36 + pub);
          }
          pub++;
          __syncwarp();
        }
        if (war < 4 - P_OB && war <= pub && (int)(ld_acquire(&g_cons[blk * 4 + war]) - target_c) >= 0) {
          war++;
          if (lane == 0) asm volatile("st.release.cta.shared.u32 [%0], %1;" ::"r"(war_ok), "r"(war) : "memory");
        }
        if (nready < NH) {
          const unsigned m = __ballot_sync(0xffffffffu, (int)(ld_acquire(fp + (nready < 24 ? (nready & ~7) : 24)) - target) >= 0);
          const unsigned both = m & (m >> 1) & 0x5555u;
          int n;
          if (nready < 24) {
            const unsigned missing = ~both & 0x5555u & (0x5555u << (2 * (nready & 7)));
            n = (nready & ~7) + (missing ? (__ffs(missing) - 1) / 2 : 8);
          } else {
            unsigned fresh = both & ~listed;
            listed |= fresh;
            n = nready;
            while (fresh) {
              const int hh = (__ffs(fresh) - 1) / 2;
              fresh &= fresh - 1;
              if (lane == 0) asm volatile("st.shared.u32 [%0], %1;" ::"r"(ord + 4 * (n - 24)), "r"(hh) : "memory");
              n++;
            }
          }
          if (n > nready) {
            nready = n;
            if (lane == 0) asm volatile("st.release.cta.shared.u32 [%0], %1;" ::"r"(ready_cnt), "r"(n) : "memory");
            if (lane == 0 && (n & 7) == 0) TL(27 + (n >> 3));
          } else {
            __nanosleep(100);
          }
        } else {
          __nanosleep(100);
        }
        if (++spins > 0x2000000u) asm volatile("trap;");
      }
      if (lane == 0) {
        __threadfence();
        if (atomicAdd(&g_done, 1u) == NCTA - 1) {
          g_done = 0;
          __threadfence();
          atomicAdd(&g_epoch, 1u);
        }
      }
    } else if (warp >= 1 && lane == 0) {
      const int pw = warp - 1;
      const CUtensorMap* mq = &maps.wq[blk];
      const CUtensorMap* mx = &maps.x[blk];
      int s = pw, ph = 1;
      int oc = pw;
      int par = 0;
#pragma unroll 1
      for (int u = 0; u < 4; u++) {
        {
          const int ch = (u * 8 + hg) * 3;
#pragma unroll 1
          for (int kc = pw ^ par; kc < 20; kc += 2) {
            const uint32_t dst = sbase + OFF_W + s * W_BYTES;
            mbar_wait(w_empty + 8 * s, ph);
            TR(8, u * 20 + kc);
            tma3d_mc(dst + rank * 6144, mq, 0, kc * 32 + rank * 16, ch, w_full + 8 * s);
            tma2d(dst + 12288, mx, kc * 32, b * SQ, w_full + 8 * s);
            mbar_expect(w_full + 8 * s, 18432);
            TR(9, u * 20 + kc);
            s += 2; if (s >= NW) { s -= NW; ph ^= 1; }
          }
        }
        if (u < 2 || !has_tile) continue;
        const int oend = u == 2 ? 3 * P_A : 3 * NH;
        const CUtensorMap* mo = &maps.wo[oblk & 1];
        const unsigned char* obase = g_oscr + (size_t)oblk * P_OB * 24 * OSC_CHUNK + oqt * 16384;
        int avail = 0;
#pragma unroll 1
        for (; oc < oend; oc += 2) {
          if (oc >= avail) {
            unsigned spins = 0;
            do {
              asm volatile("ld.acquire.cta.shared.u32 %0, [%1];" : "=r"(avail) : "r"(ready_cnt) : "memory");
              avail *= 3;
              if (++spins > 0x40000000u) asm volatile("trap;");
            } while (oc >= avail);
          }
          const uint32_t dst = sbase + OFF_W + s * W_BYTES;
          mbar_wait(w_empty + 8 * s, ph);
          if (oc < 72) {
            bulk_load_mc(dst + 8192 + rank * 8192, obase + rank * 8192 + (size_t)(oc % (24 * P_OB)) * OSC_CHUNK, 8192, w_full + 8 * s);
            tma2d(dst, mo, odt * 64, oc * 64, w_full + 8 * s);
          } else {
            int hh;
            asm volatile("ld.shared.u32 %0, [%1];" : "=r"(hh) : "r"(ord + 4 * ((oc - 72) / 3)) : "memory");
            const int o2 = 72 + hh * 3 + (oc - 72) % 3;
            bulk_load(dst + 8192, obase + (size_t)(o2 % (24 * P_OB)) * OSC_CHUNK, 16384, w_full + 8 * s);
            tma2d(dst, mo, odt * 64, o2 * 64, w_full + 8 * s);
          }
          mbar_expect(w_full + 8 * s, 24576);
          s += 2; if (s >= NW) { s -= NW; ph ^= 1; }
        }
        par = (3 * P_A) & 1;
      }
    }
    __syncwarp();
    cluster_sync();
  } else if (wg == 1) {
    asm volatile("setmaxnreg.inc.sync.aligned.u32 %0;" ::"n"(REG_PROJ));
    float acc_o[64];
    int s = 0, ph = 0;
    int prev = -1;
    bool first_o = true;
    const uint32_t w4 = (sbase + OFF_W) >> 4;
    bool nxt_ok = false;
#define W_SLOT(MMAS_A, MMAS_B)                                                          \
    {                                                                                   \
      const uint32_t a4 = w4 + s * (W_BYTES >> 4);                                      \
      if (!nxt_ok) mbar_wait(w_full + 8 * s, ph);                                       \
      wg_fence();                                                                       \
      MMAS_A                                                                            \
      wg_wait<0>();                                                                     \
      if (prev >= 0 && tid == 128) mbar_arrive_pair(w_empty + 8 * prev, peer);          \
      prev = s;                                                                         \
      if (++s == NW) { s = 0; ph ^= 1; }                                                \
      nxt_ok = __all_sync(0xffffffffu, mbar_test(w_full + 8 * s, ph));                  \
      MMAS_B                                                                            \
      wg_commit();                                                                      \
    }
#define W_DRAIN()                                                                       \
    {                                                                                   \
      wg_wait<0>();                                                                     \
      if (prev >= 0 && tid == 128) mbar_arrive_pair(w_empty + 8 * prev, peer);          \
      prev = -1;                                                                        \
    }
#define Q_STORE()                                                                       \
    {                                                                                   \
      store_tile_T<12>(qa, sbase + OFF_Q, warp, lane);                                  \
      store_tile_T<12>(qb, sbase + OFF_Q + QC_BYTES, warp, lane);                       \
      store_tile_T<12>(qc, sbase + OFF_Q + 2 * QC_BYTES, warp, lane);                   \
      asm volatile("fence.proxy.async.shared::cta;" ::: "memory");                      \
      mbar_arrive(q_ready);                                                             \
    }
#pragma unroll 1
    for (int u = 0; u < 4; u++) {
      float qa[48], qb[48], qc[48];
#pragma unroll 1
      for (int kc = 0; kc < 20; kc++)
#define Q_MMAS(KK)                                                                      \
          {                                                                             \
            const uint64_t db = desc64(a4 + 768 + (KK) * 2);                            \
            wgmma_q96(qa, desc(a4 + (KK) * 384), db, (kc | (KK)) != 0);                 \
            wgmma_q96(qb, desc(a4 + (KK) * 384 + 128), db, (kc | (KK)) != 0);           \
            wgmma_q96(qc, desc(a4 + (KK) * 384 + 256), db, (kc | (KK)) != 0);           \
          }
        W_SLOT(Q_MMAS(0), Q_MMAS(1))
      W_DRAIN()
      fence_regs(qa); fence_regs(qb); fence_regs(qc);
      if (tid == 128) TL(8 + 2 * u);
      bool pending = true;
      const int n_o = (!has_tile || u < 2) ? 0 : (u == 2 ? 3 * P_A : 3 * (NH - P_A));
#pragma unroll 1
      for (int it = 0; it < n_o; it++) {
        if (pending && !nxt_ok) {
          unsigned spins = 0;
          while (!__all_sync(0xffffffffu, mbar_test(w_full + 8 * s, ph))) {
            if (__all_sync(0xffffffffu, mbar_test(q_free, (u - 1) & 1))) { Q_STORE() pending = false; break; }
            if (++spins > 0x10000000u) asm volatile("trap;");
          }
        }
        W_SLOT(wgmma_o128(acc_o, desc(a4), desc(a4 + 512), !first_o); wgmma_o128(acc_o, desc(a4 + 128), desc(a4 + 514), 1);,
               wgmma_o128(acc_o, desc(a4 + 256), desc(a4 + 516), 1); wgmma_o128(acc_o, desc(a4 + 384), desc(a4 + 518), 1);)
        first_o = false;
        if (tid == 128) {
          const int gi = it + 1 + (u == 3 ? 3 * P_A : 0);
          if (gi % 24 == 0) asm volatile("red.release.gpu.global.add.u32 [%0], 1;" ::"l"(&g_cons[oblk * 4 + gi / 24 - 1]) : "memory");
        }
        if (pending && __all_sync(0xffffffffu, mbar_test(q_free, (u - 1) & 1))) {
          Q_STORE()
          pending = false;
        }
      }
      W_DRAIN()
      fence_regs(acc_o);
      if (pending) {
        if (u > 0) mbar_wait(q_free, (u - 1) & 1);
        Q_STORE()
      }
      if (tid == 128) TL(9 + 2 * u);
    }
    if (has_tile) {
      const uint32_t st = sbase + OFF_W;
      asm volatile("bar.sync 3, 128;" ::: "memory");
      store_tile_T<16>(acc_o, st, warp, lane);
      asm volatile("bar.sync 3, 128;" ::: "memory");
      const int t = tid & 127, unit = t & 7;
#pragma unroll
      for (int i = 0; i < 8; i++) {
        const int q = (t >> 3) + 16 * i;
        uint4 v;
        asm volatile("ld.shared.v4.u32 {%0,%1,%2,%3}, [%4];" : "=r"(v.x), "=r"(v.y), "=r"(v.z), "=r"(v.w) : "r"(st + q * 128 + ((unit ^ (q & 7)) << 4)));
        *reinterpret_cast<uint4*>(out + (size_t)(oqt * 128 + q) * (2 * DM) + oblk * DM + odt * 64 + unit * 8) = v;
      }
      if (tid == 128) { TL(24); TLV(2, CLK()); }
    }
    cluster_sync();
  } else {
    asm volatile("setmaxnreg.inc.sync.aligned.u32 %0;" ::"n"(REG_ATTN));
    const float cs = 0.07216878364870322f * 1.4426950408889634f;
    const int c = lane & 3;
    const bool elect = tid == 0;
    const bool h4 = lane & 16, h3 = lane & 8, h2 = lane & 4;
    float o0[48], o1[48], o2[48];
    const uint32_t kv4 = (sbase + OFF_KV) >> 4, q4 = (sbase + OFF_Q) >> 4, p4 = (sbase + OFF_P) >> 4;
    unsigned char* sgen = smem_raw;
    float* wsum = reinterpret_cast<float*>(sgen + OFF_ST);
    int* wmax = reinterpret_cast<int*>(sgen + OFF_ST + 1536);
    float2* nbv = reinterpret_cast<float2*>(sgen + OFF_ST + 1920);
    float2* fsc = reinterpret_cast<float2*>(sgen + OFF_ST + 2304);
    const int idx0 = (h4 ? 12 : 0) + (h3 ? 6 : 0) + (h2 ? 3 : 0) + c * 24;
    const int own = ((tid >> 1) & 3) * 24 + (tid >> 3) * 2 + (tid & 1);
    if (tid < SQ) wmax[tid] = (int)0x80000000;
    asm volatile("bar.sync 1, 128;" ::: "memory");
    const uint32_t st_addr = sbase + OFF_P + ((lane & 7) + ((lane >> 4) ? 48 : 0)) * 128 + (((2 * warp + ((lane >> 3) & 1)) ^ (lane & 7)) << 4);
    int s = 0, ph = 0;
#define NEXT_PIECE() { if (++s == NP) { s = 0; ph ^= 1; } }
#define ABAR() asm volatile("bar.sync 1, 128;" ::: "memory")
#define BFLY_TAIL(OP, STORE)                                                                                     \
    {                                                                                                          \
      float b_[6], c_[3];                                                                                      \
      _Pragma("unroll") for (int i = 0; i < 6; i++) {                                                          \
        const float snd = h3 ? a[i] : a[6 + i], kp = h3 ? a[6 + i] : a[i];                                     \
        b_[i] = OP(kp, __shfl_xor_sync(0xffffffffu, snd, 8));                                                  \
      }                                                                                                        \
      _Pragma("unroll") for (int i = 0; i < 3; i++) {                                                          \
        const float snd = h2 ? b_[i] : b_[3 + i], kp = h2 ? b_[3 + i] : b_[i];                                 \
        c_[i] = OP(kp, __shfl_xor_sync(0xffffffffu, snd, 4));                                                  \
      }                                                                                                        \
      _Pragma("unroll") for (int i = 0; i < 3; i++) { STORE }                                                  \
    }
#define FADD2(x, y) ((x) + (y))
#pragma unroll 1
    for (int u = 0; u < 4; u++) {
      float nb_run = 0.f;
      float lsum[3] = {0.f, 0.f, 0.f};
      mbar_wait(q_ready, u & 1);
      if (tid == 0) TL(16 + u);
#pragma unroll 1
      for (int j = 0; j < 8; j++) {
        float sc[48];
        {
          const int s0 = s;
          if (tid == 0) TR(0, u * 8 + j);
          mbar_wait(kv_full + 8 * s, ph);
          if (tid == 0) TR(1, u * 8 + j);
          wg_fence();
#pragma unroll
          for (int kk = 0; kk < 4; kk++) wgmma_s96(sc, desc(kv4 + s0 * 512 + kk * 2), desc(q4 + kk * 2), kk != 0);
          wg_commit();
          NEXT_PIECE()
          const int s1 = s;
          mbar_wait(kv_full + 8 * s, ph);
#pragma unroll
          for (int kk = 0; kk < 4; kk++) wgmma_s96(sc, desc(kv4 + s1 * 512 + kk * 2), desc(q4 + 768 + kk * 2), 1);
          wg_commit();
          NEXT_PIECE()
          const int s2 = s;
          mbar_wait(kv_full + 8 * s, ph);
#pragma unroll
          for (int kk = 0; kk < 4; kk++) wgmma_s96(sc, desc(kv4 + s2 * 512 + kk * 2), desc(q4 + 1536 + kk * 2), 1);
          wg_commit();
          NEXT_PIECE()
          wg_wait<2>();
          if (elect) mbar_arrive(kv_empty + 8 * s0);
          wg_wait<1>();
          if (elect) mbar_arrive(kv_empty + 8 * s1);
          wg_wait<0>();
          if (elect) {
            mbar_arrive(kv_empty + 8 * s2);
            if (j == 7) mbar_arrive(q_free);
          }
        }
        fence_regs(sc);
        if (tid == 0) TR(2, u * 8 + j);
        bool move = true;
        {
          float mx = -INFINITY;
#pragma unroll
          for (int ja = 0; ja < 12; ja++) {
            float2 nb = make_float2(0.f, 0.f);
            if (j > 0) nb = nbv[4 * ja + c];
            sc[4 * ja] = fmaf(sc[4 * ja], cs, nb.x); sc[4 * ja + 1] = fmaf(sc[4 * ja + 1], cs, nb.y);
            sc[4 * ja + 2] = fmaf(sc[4 * ja + 2], cs, nb.x); sc[4 * ja + 3] = fmaf(sc[4 * ja + 3], cs, nb.y);
            mx = fmaxf(mx, fmaxf(fmaxf(sc[4 * ja], sc[4 * ja + 1]), fmaxf(sc[4 * ja + 2], sc[4 * ja + 3])));
          }
          if (j > 0) {
            uint32_t r;
            asm volatile("{\n.reg .pred p, q;\nsetp.ne.u32 q, %1, 0;\nbar.red.or.pred p, 1, 128, q;\nselp.u32 %0, 1, 0, p;\n}\n"
                         : "=r"(r) : "r"((uint32_t)!(mx <= 8.f)) : "memory");
            move = r != 0;
          }
        }
        if (move) {
          {
            float a[12];
#pragma unroll
            for (int i = 0; i < 12; i++) {
              const int ja = i >> 1, e = i & 1;
              const float x = fmaxf(sc[4 * ja + e], sc[4 * ja + 2 + e]), y = fmaxf(sc[4 * (ja + 6) + e], sc[4 * (ja + 6) + 2 + e]);
              a[i] = fmaxf(h4 ? y : x, __shfl_xor_sync(0xffffffffu, h4 ? x : y, 16));
            }
            BFLY_TAIL(fmaxf, const int bits = __float_as_int(c_[i]); atomicMax(wmax + idx0 + i, bits >= 0 ? bits : bits ^ 0x7fffffff);)
          }
          ABAR();
          if (tid < SQ) {
            const int key = wmax[own];
            wmax[own] = (int)0x80000000;
            float d = __int_as_float(key >= 0 ? key : key ^ 0x7fffffff);
            if (j > 0) d = fmaxf(d, 0.f); else nb_run = 0.f;
            nb_run -= d;
            reinterpret_cast<float*>(nbv)[tid] = nb_run;
            reinterpret_cast<float*>(fsc)[tid] = d;
            wsum[own] = d;
          }
          ABAR();
#pragma unroll
          for (int ja = 0; ja < 12; ja++) {
            const float2 d = fsc[4 * ja + c];
            sc[4 * ja] -= d.x; sc[4 * ja + 1] -= d.y; sc[4 * ja + 2] -= d.x; sc[4 * ja + 3] -= d.y;
            if (j > 0) {
              const float f0 = ex2(-d.x), f1 = ex2(-d.y);
              o0[4 * ja] *= f0; o0[4 * ja + 1] *= f1; o0[4 * ja + 2] *= f0; o0[4 * ja + 3] *= f1;
              o1[4 * ja] *= f0; o1[4 * ja + 1] *= f1; o1[4 * ja + 2] *= f0; o1[4 * ja + 3] *= f1;
              o2[4 * ja] *= f0; o2[4 * ja + 1] *= f1; o2[4 * ja + 2] *= f0; o2[4 * ja + 3] *= f1;
            }
          }
#pragma unroll
          for (int i = 0; i < 3; i++) lsum[i] = j > 0 ? lsum[i] * ex2(-wsum[idx0 + i]) : 0.f;
        }
        float a[12];
        {
          uint32_t pk[24];
#pragma unroll
          for (int jj = 0; jj < 6; jj++) {
            float sm[4];
#pragma unroll
            for (int hh = 0; hh < 2; hh++) {
              const int ja = jj + 6 * hh;
              const float p00 = ex2(sc[4 * ja]), p01 = ex2(sc[4 * ja + 1]), p10 = ex2(sc[4 * ja + 2]), p11 = ex2(sc[4 * ja + 3]);
              pk[4 * jj + 2 * hh] = pack_bf16(p00, p01); pk[4 * jj + 2 * hh + 1] = pack_bf16(p10, p11);
              sm[2 * hh] = p00 + p10; sm[2 * hh + 1] = p01 + p11;
            }
#pragma unroll
            for (int e = 0; e < 2; e++)
              a[2 * jj + e] = (h4 ? sm[2 + e] : sm[e]) + __shfl_xor_sync(0xffffffffu, h4 ? sm[e] : sm[2 + e], 16);
          }
#pragma unroll
          for (int jj = 0; jj < 6; jj++) stsm_x4_t(st_addr + jj * 1024, pk[4 * jj], pk[4 * jj + 1], pk[4 * jj + 2], pk[4 * jj + 3]);
          asm volatile("fence.proxy.async.shared::cta;" ::: "memory");
        }
        ABAR();
        if (tid == 0) TR(3, u * 8 + j);
        {
#define PV_CHUNK(OC, SS)                                                                                             \
          const int SS = s;                                                                                          \
          mbar_wait(kv_full + 8 * s, ph);                                                                            \
          _Pragma("unroll") for (int kk = 0; kk < 4; kk++)                                                           \
            wgmma_q96(OC, desc(kv4 + SS * 512 + kk * 128), desc(p4 + kk * 2), (j | kk) != 0);                        \
          wg_commit();                                                                                               \
          NEXT_PIECE()
          wg_fence();
          PV_CHUNK(o0, s0)
          if (tid == 0) TR(4, u * 8 + j);
          BFLY_TAIL(FADD2, lsum[i] += c_[i];)
          PV_CHUNK(o1, s1)
          PV_CHUNK(o2, s2)
          wg_wait<2>();
          if (elect) mbar_arrive(kv_empty + 8 * s0);
          wg_wait<1>();
          if (elect) mbar_arrive(kv_empty + 8 * s1);
          wg_wait<0>();
          if (elect) mbar_arrive(kv_empty + 8 * s2);
        }
        fence_regs(o0); fence_regs(o1); fence_regs(o2);
        if (tid == 0) TR(5, u * 8 + j);
      }
#pragma unroll
      for (int i = 0; i < 3; i++) wsum[warp * 96 + idx0 + i] = lsum[i];
      ABAR();
      if (tid < SQ) reinterpret_cast<float*>(nbv)[tid] = 1.f / ((wsum[own] + wsum[own + 96]) + (wsum[own + 192] + wsum[own + 288]));
      ABAR();
      if (u >= P_OB) smem_wait_ge(war_ok, u - P_OB + 1);
      unsigned char* dst = g_oscr + (size_t)(((blk * P_OB + u % P_OB) * 8 + hg) * 3) * OSC_CHUNK + (size_t)b * SQ * 128 + tid * 16;
#define O_STORE(OC, CC)                                                                                              \
      {                                                                                                              \
        uint32_t pk[24];                                                                                             \
        _Pragma("unroll") for (int jj = 0; jj < 6; jj++) {                                                           \
          _Pragma("unroll") for (int hh = 0; hh < 2; hh++) {                                                         \
            const int ja = jj + 6 * hh;                                                                              \
            const float2 iv = nbv[4 * ja + c];                                                                       \
            pk[4 * jj + 2 * hh] = pack_bf16(OC[4 * ja] * iv.x, OC[4 * ja + 1] * iv.y);                               \
            pk[4 * jj + 2 * hh + 1] = pack_bf16(OC[4 * ja + 2] * iv.x, OC[4 * ja + 3] * iv.y);                       \
          }                                                                                                          \
        }                                                                                                            \
        if (CC > 0) ABAR();                                                                                          \
        _Pragma("unroll") for (int jj = 0; jj < 6; jj++)                                                             \
          stsm_x4_t(st_addr + jj * 1024, pk[4 * jj], pk[4 * jj + 1], pk[4 * jj + 2], pk[4 * jj + 3]);                \
        ABAR();                                                                                                      \
        _Pragma("unroll") for (int i = 0; i < 6; i++) {                                                              \
          const uint4 v = *reinterpret_cast<const uint4*>(sgen + OFF_P + tid * 16 + i * 2048);                       \
          *reinterpret_cast<uint4*>(dst + (size_t)CC * OSC_CHUNK + i * 2048) = v;                                    \
        }                                                                                                            \
      }
      O_STORE(o0, 0)
      O_STORE(o1, 1)
      O_STORE(o2, 2)
      mbar_arrive(o_done);
      if (tid == 0) TL(20 + u);
    }
    __syncwarp();
    cluster_sync();
  }
}

__device__ __nv_bfloat16 g_fq[768 * 6144];
__device__ __nv_bfloat16 g_fo[768 * 6144];
__global__ void fb_gemm(const __nv_bfloat16* __restrict__ a, const __nv_bfloat16* __restrict__ w, __nv_bfloat16* __restrict__ c,
                        int K, int N, int ldc) {
  const int n = blockIdx.x * blockDim.x + threadIdx.x, r = blockIdx.y;
  float acc = 0.f;
  for (int k = 0; k < K; k++) acc = fmaf(__bfloat162float(a[(size_t)r * K + k]), __bfloat162float(w[(size_t)k * N + n]), acc);
  c[(size_t)r * ldc + n] = __float2bfloat16(acc);
}
__global__ void fb_attn(const __nv_bfloat16* __restrict__ kc, const __nv_bfloat16* __restrict__ vc) {
  __shared__ float p[SK], red[SK], qs[DH];
  const int r = blockIdx.x, h = blockIdx.y, b = r / SQ, t = threadIdx.x;
  if (t < DH) qs[t] = __bfloat162float(g_fq[(size_t)r * (NH * DH) + h * DH + t]);
  __syncthreads();
  const __nv_bfloat16* kr = kc + ((size_t)(b * NH + h) * SK + t) * DH;
  float s = 0.f;
  for (int d = 0; d < DH; d++) s = fmaf(qs[d], __bfloat162float(kr[d]), s);
  s *= 0.07216878364870322f;
  red[t] = s; __syncthreads();
  for (int o = SK / 2; o > 0; o >>= 1) { if (t < o) red[t] = fmaxf(red[t], red[t + o]); __syncthreads(); }
  const float m = red[0]; __syncthreads();
  const float e = expf(s - m);
  p[t] = e; red[t] = e; __syncthreads();
  for (int o = SK / 2; o > 0; o >>= 1) { if (t < o) red[t] += red[t + o]; __syncthreads(); }
  if (t < DH) {
    const __nv_bfloat16* vr = vc + (size_t)(b * NH + h) * SK * DH + t;
    float a = 0.f;
    for (int k = 0; k < SK; k++) a = fmaf(p[k], __bfloat162float(vr[(size_t)k * DH]), a);
    g_fo[(size_t)r * (NH * DH) + h * DH + t] = __float2bfloat16(a / red[0]);
  }
}

typedef CUresult (*EncodeFn)(CUtensorMap*, CUtensorMapDataType, cuuint32_t, void*, const cuuint64_t*, const cuuint64_t*,
                             const cuuint32_t*, const cuuint32_t*, CUtensorMapInterleave, CUtensorMapSwizzle,
                             CUtensorMapL2promotion, CUtensorMapFloatOOBfill);

void make_map(EncodeFn fn, CUtensorMap* m, const void* ptr, cuuint64_t cols, cuuint64_t rows, cuuint32_t bcols, cuuint32_t brows,
              CUtensorMapSwizzle swz) {
  cuuint64_t dims[2] = {cols, rows};
  cuuint64_t str[1] = {cols * 2};
  cuuint32_t box[2] = {bcols, brows};
  cuuint32_t es[2] = {1, 1};
  fn(m, CU_TENSOR_MAP_DATA_TYPE_BFLOAT16, 2, const_cast<void*>(ptr), dims, str, box, es, CU_TENSOR_MAP_INTERLEAVE_NONE, swz,
     CU_TENSOR_MAP_L2_PROMOTION_L2_128B, CU_TENSOR_MAP_FLOAT_OOB_FILL_NONE);
}
void make_map_wq(EncodeFn fn, CUtensorMap* m, const void* ptr) {
  cuuint64_t dims[3] = {64, DM, NH * 3};
  cuuint64_t str[2] = {(cuuint64_t)NH * DH * 2, 128};
  cuuint32_t box[3] = {64, 16, 3};
  cuuint32_t es[3] = {1, 1, 1};
  CUresult r = fn(m, CU_TENSOR_MAP_DATA_TYPE_BFLOAT16, 3, const_cast<void*>(ptr), dims, str, box, es, CU_TENSOR_MAP_INTERLEAVE_NONE,
     CU_TENSOR_MAP_SWIZZLE_128B, CU_TENSOR_MAP_L2_PROMOTION_L2_128B, CU_TENSOR_MAP_FLOAT_OOB_FILL_NONE);
  (void)r;
}

}

extern "C" void kernel_launch(void* const* d_in, const int* in_sizes, int n_in, void* d_out, int out_size) {
  static Maps maps;
  static const void* cached[10] = {nullptr};
  static EncodeFn fn = nullptr;
  static bool init = false, use_fused = false;
  if (!init) {
    void* p = nullptr;
    cudaDriverEntryPointQueryResult qr;
    cudaGetDriverEntryPoint("cuTensorMapEncodeTiled", &p, cudaEnableDefault, &qr);
    fn = (EncodeFn)p;
    cudaFuncSetAttribute(fused_mha_kernel, cudaFuncAttributeMaxDynamicSharedMemorySize, SMEM_BYTES);
    cudaLaunchConfig_t cfg = {};
    cfg.gridDim = dim3(NCTA); cfg.blockDim = dim3(384); cfg.dynamicSmemBytes = SMEM_BYTES;
    cudaLaunchAttribute at[1];
    at[0].id = cudaLaunchAttributeClusterDimension;
    at[0].val.clusterDim.x = 2; at[0].val.clusterDim.y = 1; at[0].val.clusterDim.z = 1;
    cfg.attrs = at; cfg.numAttrs = 1;
    int ncl = 0;
    use_fused = fn != nullptr && cudaOccupancyMaxActiveClusters(&ncl, fused_mha_kernel, &cfg) == cudaSuccess && ncl >= NCTA / 2;
    init = true;
  }
  if (!use_fused) {
    void *fq, *fo;
    cudaGetSymbolAddress(&fq, g_fq); cudaGetSymbolAddress(&fo, g_fo);
    for (int blk = 0; blk < 2; blk++) {
      void* const* in = d_in + 5 * blk;
      fb_gemm<<<dim3(24, 768), 256>>>((const __nv_bfloat16*)in[0], (const __nv_bfloat16*)in[3], (__nv_bfloat16*)fq, DM, NH * DH, NH * DH);
      fb_attn<<<dim3(768, NH), SK>>>((const __nv_bfloat16*)in[1], (const __nv_bfloat16*)in[2]);
      fb_gemm<<<dim3(5, 768), 128>>>((const __nv_bfloat16*)fo, (const __nv_bfloat16*)in[4], (__nv_bfloat16*)d_out + blk * DM, NH * DH, DM, 2 * DM);
    }
    return;
  }
  bool same = true;
  for (int i = 0; i < 10; i++) same = same && (cached[i] == d_in[i]);
  if (!same) {
    for (int blk = 0; blk < 2; blk++) {
      void* const* in = d_in + 5 * blk;
      make_map(fn, &maps.k[blk], in[1], DH, (cuuint64_t)NB * NH * SK, 64, 64, CU_TENSOR_MAP_SWIZZLE_128B);
      make_map(fn, &maps.v[blk], in[2], DH, (cuuint64_t)NB * NH * SK, 64, 64, CU_TENSOR_MAP_SWIZZLE_128B);
      make_map_wq(fn, &maps.wq[blk], in[3]);
      make_map(fn, &maps.x[blk], in[0], DM, NB * SQ, 32, SQ, CU_TENSOR_MAP_SWIZZLE_64B);
      make_map(fn, &maps.wo[blk], in[4], DM, NH * DH, 64, 64, CU_TENSOR_MAP_SWIZZLE_128B);
    }
    for (int i = 0; i < 10; i++) cached[i] = d_in[i];
  }
  fused_mha_kernel<<<NCTA, 384, SMEM_BYTES>>>(maps, (__nv_bfloat16*)d_out);
}
```
